```python
import torch

def _softmax(x, axis=-1):
    return torch.softmax(x, dim=axis)
def _gelu(x):
    return torch.nn.functional.gelu(x, approximate="tanh")
def _silu(x):
    return torch.nn.functional.silu(x)
def _sigmoid(x):
    return torch.sigmoid(x)
def _layernorm(x, axis=-1, eps=1e-5):
    m = x.mean(dim=axis, keepdim=True)
    v = x.var(dim=axis, keepdim=True, unbiased=False)
    return (x - m) / torch.sqrt(v + eps)
def _scatter_add(tgt, idx, src, axis=0):
    return tgt.clone().index_add_(axis, idx, src)
def _segment_sum(src, seg, n):
    out = torch.zeros((n,) + src.shape[1:], dtype=src.dtype)
    return out.index_add_(0, seg, src)
def _pad(x, pw):
    flat = tuple(v for pair in reversed(pw) for v in pair)
    return torch.nn.functional.pad(x, flat)

kernel_name = 'concat_heads__softmax_full_mha__compressed_kv_cla__prompt'

def setup_inputs():

    _w = (lambda a: (lambda t: t.to(torch.bfloat16) if t.is_floating_point() else t)(torch.as_tensor(a)))
    def _A_setup():
        B, S, D = 1, 2048, 448
        return {
            "x": _w((lambda *s: torch.randn(*s, dtype=torch.bfloat16) * 0.4)(B, S, D)),
            "wqkv": _w((lambda *s: torch.randn(*s, dtype=torch.bfloat16) * 0.4)(D, 3 * D)),
            "wo": _w((lambda *s: torch.randn(*s, dtype=torch.bfloat16) * 0.05)(D, D)),
        }
    _A_in = _A_setup()

    def _B_setup():
        B, H, Sq, Sk, D, M = 1, 16, 2048, 2048, 256, 448
        Dc = 4 * D
        return {
            "x": _w((lambda *s: torch.randn(*s, dtype=torch.bfloat16) * 0.2)(B, Sq, M)),
            "c_kv": _w((lambda *s: torch.randn(*s, dtype=torch.bfloat16) * 1.6)(B, Sk, Dc)),
            "w_q": _w((lambda *s: torch.randn(*s, dtype=torch.bfloat16) * 3.2)(M, H, D) * (M ** -0.5)),
            "w_uk": _w((lambda *s: torch.randn(*s, dtype=torch.bfloat16) * 3.2)(Dc, H, D) * (Dc ** -0.5)),
            "w_uv": _w((lambda *s: torch.randn(*s, dtype=torch.bfloat16) * 1.6)(Dc, H, D) * (Dc ** -0.5)),
            "w_o": _w((lambda *s: torch.randn(*s, dtype=torch.bfloat16) * 1.6)(H, D, M) * ((H * D) ** -0.5)),
        }
    _B_in = _B_setup()

    return {
        "A_x": _A_in["x"],
        "A_wqkv": _A_in["wqkv"],
        "A_wo": _A_in["wo"],
        "B_x": _B_in["x"],
        "B_c_kv": _B_in["c_kv"],
        "B_w_q": _B_in["w_q"],
        "B_w_uk": _B_in["w_uk"],
        "B_w_uv": _B_in["w_uv"],
        "B_w_o": _B_in["w_o"],
    }

def reference(A_x, A_wqkv, A_wo, B_x, B_c_kv, B_w_q, B_w_uk, B_w_uv, B_w_o):
    def _A_ref(x, wqkv, wo):
        B, S, D = x.shape
        H = 16; Dh = D // H
        qkv = (lambda x, *d: x.permute(*d))((x @ wqkv).reshape(B, S, 3, H, Dh), 2, 0, 3, 1, 4)
        q, k, v = qkv[0], qkv[1], qkv[2]
        scale = Dh ** -0.5
        scores = torch.einsum("bhqd,bhkd->bhqk", q, k) * scale
        p = _softmax(scores, axis=-1)
        o = torch.einsum("bhqk,bhkd->bhqd", p, v)
        return (lambda x, *d: x.permute(*d))(o, 0, 2, 1, 3).reshape(B, S, D) @ wo

    def _B_ref(x, c_kv, w_q, w_uk, w_uv, w_o):
        B, Sq, M = x.shape[0], x.shape[1], x.shape[2]
        Sk = c_kv.shape[1]
        H, D = w_q.shape[1], w_q.shape[2]
        q = torch.einsum("bqm,mhd->bhqd", x, w_q)
        k = torch.einsum("bkc,chd->bhkd", c_kv, w_uk)
        v = torch.einsum("bkc,chd->bhkd", c_kv, w_uv)
        scores = torch.einsum("bhqd,bhkd->bhqk", q, k) * (D ** -0.5)
        off = Sk - Sq
        qi = torch.arange(Sq)[:, None]
        kj = torch.arange(Sk)[None, :]
        cmask = kj <= (qi + off)
        scores = torch.where(cmask[None, None], scores, -1e9)
        p = _softmax(scores, axis=-1)
        ctx = torch.einsum("bhqk,bhkd->bhqd", p, v)
        return torch.einsum("bhqd,hdm->bqm", ctx, w_o)

    a = _A_ref(A_x, A_wqkv, A_wo)
    b = _B_ref(B_x, B_c_kv, B_w_q, B_w_uk, B_w_uv, B_w_o)
    return torch.concatenate([a, b], axis=-1)
```

```cpp
#include <cuda_runtime.h>
#include <cuda_bf16.h>
#include <cuda.h>
#include <stdint.h>
#include <math.h>

typedef __nv_bfloat16 bf16;

__device__ __forceinline__ uint32_t smem_u32(const void* p) { return (uint32_t)__cvta_generic_to_shared(p); }

__device__ __forceinline__ void mbar_init(uint32_t bar, uint32_t cnt) {
  asm volatile("mbarrier.init.shared::cta.b64 [%0], %1;" ::"r"(bar), "r"(cnt));
}
__device__ __forceinline__ void mbar_expect_tx(uint32_t bar, uint32_t bytes) {
  asm volatile("mbarrier.arrive.expect_tx.shared::cta.b64 _, [%0], %1;" ::"r"(bar), "r"(bytes) : "memory");
}
__device__ __forceinline__ void mbar_arrive(uint32_t bar) {
  asm volatile("mbarrier.arrive.shared::cta.b64 _, [%0];" ::"r"(bar) : "memory");
}
__device__ __forceinline__ void mbar_arrive_cluster(uint32_t cbar) {
  asm volatile("mbarrier.arrive.shared::cluster.b64 _, [%0];" ::"r"(cbar) : "memory");
}
__device__ __forceinline__ uint32_t mapa(uint32_t addr, uint32_t cta) {
  uint32_t r;
  asm("mapa.shared::cluster.u32 %0, %1, %2;" : "=r"(r) : "r"(addr), "r"(cta));
  return r;
}
__device__ __forceinline__ void mbar_wait(uint32_t bar, uint32_t parity) {
  asm volatile(
      "{\n.reg .pred P1;\n.reg .u32 cnt;\nmov.u32 cnt, 0;\n"
      "LAB_WAIT:\n"
      "mbarrier.try_wait.parity.shared::cta.b64 P1, [%0], %1;\n"
      "@P1 bra DONE;\n"
      "add.u32 cnt, cnt, 1;\n"
      "setp.lt.u32 P1, cnt, 4194304;\n"
      "@P1 bra LAB_WAIT;\n"
      "trap;\n"
      "DONE:\n}" ::"r"(bar), "r"(parity) : "memory");
}

__device__ __forceinline__ void tma_load_2d(uint32_t dst, const CUtensorMap* tm, uint32_t bar, int c0, int c1) {
  asm volatile(
      "cp.async.bulk.tensor.2d.shared::cluster.global.mbarrier::complete_tx::bytes [%0], [%1, {%3, %4}], [%2];"
      ::"r"(dst), "l"(tm), "r"(bar), "r"(c0), "r"(c1) : "memory");
}
__device__ __forceinline__ void tma_load_2d_mc(uint32_t dst, const CUtensorMap* tm, uint32_t bar, int c0, int c1,
                                               uint16_t mask) {
  asm volatile(
      "cp.async.bulk.tensor.2d.shared::cluster.global.mbarrier::complete_tx::bytes.multicast::cluster"
      " [%0], [%1, {%3, %4}], [%2], %5;"
      ::"r"(dst), "l"(tm), "r"(bar), "r"(c0), "r"(c1), "h"(mask) : "memory");
}
__device__ __forceinline__ void tma_store_2d(const CUtensorMap* tm, uint32_t src, int c0, int c1) {
  asm volatile("cp.async.bulk.tensor.2d.global.shared::cta.bulk_group [%0, {%2, %3}], [%1];"
               ::"l"(tm), "r"(src), "r"(c0), "r"(c1) : "memory");
}
__device__ __forceinline__ void tma_store_commit() { asm volatile("cp.async.bulk.commit_group;" ::: "memory"); }
template <int N> __device__ __forceinline__ void tma_store_wait_read() {
  asm volatile("cp.async.bulk.wait_group.read %0;" ::"n"(N) : "memory");
}
template <int N> __device__ __forceinline__ void tma_store_wait() {
  asm volatile("cp.async.bulk.wait_group %0;" ::"n"(N) : "memory");
}
__device__ __forceinline__ void tma_prefetch_desc(const CUtensorMap* tm) {
  asm volatile("prefetch.tensormap [%0];" ::"l"(tm) : "memory");
}
__device__ __forceinline__ void fence_proxy_async() { asm volatile("fence.proxy.async.shared::cta;" ::: "memory"); }
__device__ __forceinline__ void fence_barrier_init() { asm volatile("fence.mbarrier_init.release.cluster;" ::: "memory"); }
__device__ __forceinline__ uint32_t cluster_ctarank() {
  uint32_t r;
  asm("mov.u32 %0, %%cluster_ctarank;" : "=r"(r));
  return r;
}
__device__ __forceinline__ void named_bar_sync(int id, int nthreads) {
  asm volatile("bar.sync %0, %1;" ::"r"(id), "r"(nthreads) : "memory");
}

__device__ __forceinline__ void wg_fence() { asm volatile("wgmma.fence.sync.aligned;" ::: "memory"); }
__device__ __forceinline__ void wg_commit() { asm volatile("wgmma.commit_group.sync.aligned;" ::: "memory"); }
template <int N> __device__ __forceinline__ void wg_wait() {
  asm volatile("wgmma.wait_group.sync.aligned %0;" ::"n"(N) : "memory");
}
template <int N> __device__ __forceinline__ void reg_fence(float (&d)[N]) {
#pragma unroll
  for (int i = 0; i < N; i++) asm volatile("" : "+f"(d[i])::"memory");
}
template <int N> __device__ __forceinline__ void reg_fence(uint32_t (&d)[N]) {
#pragma unroll
  for (int i = 0; i < N; i++) asm volatile("" : "+r"(d[i])::"memory");
}

__device__ __forceinline__ uint64_t desc_make(uint32_t lo, uint32_t hi) { return ((uint64_t)hi << 32) | lo; }
constexpr uint32_t DESC_HI_SW128 = 0x40000000u | (1024u >> 4);
constexpr uint32_t DESC_HI_SW64 = 0x80000000u | (512u >> 4);
__device__ __forceinline__ uint32_t a16(uint32_t addr) { return (addr & 0x3FFFFu) >> 4; }
__device__ __forceinline__ uint64_t desc_k128(uint32_t u) { return desc_make(u + (1u << 16), DESC_HI_SW128); }
__device__ __forceinline__ uint64_t desc_64(uint32_t u) { return desc_make(u + (1u << 16), DESC_HI_SW64); }

__device__ __forceinline__ uint32_t pack_bf16(float lo, float hi) {
  uint32_t r;
  asm("cvt.rn.bf16x2.f32 %0, %1, %2;" : "=r"(r) : "f"(hi), "f"(lo));
  return r;
}
__device__ __forceinline__ float ex2(float x) {
  float r;
  asm("ex2.approx.ftz.f32 %0, %1;" : "=f"(r) : "f"(x));
  return r;
}
__device__ __forceinline__ void stmatrix_x4(uint32_t addr, uint32_t r0, uint32_t r1, uint32_t r2, uint32_t r3) {
  asm volatile("stmatrix.sync.aligned.m8n8.x4.shared.b16 [%0], {%1, %2, %3, %4};"
               ::"r"(addr), "r"(r0), "r"(r1), "r"(r2), "r"(r3) : "memory");
}

template <int G0, int NG, int NACC>
__device__ __forceinline__ void store_acc_sw128(const float (&acc)[NACC], uint32_t base, int warp_in_wg, int lane,
                                                float s0, float s1) {
  const int mi = lane >> 3;
  const int row = warp_in_wg * 16 + (mi & 1) * 8 + (lane & 7);
  const uint32_t rowaddr = base + row * 128;
  const int hi = mi >> 1;
  const int r7 = lane & 7;
#pragma unroll
  for (int g = 0; g < NG; g += 2) {
    const int j = G0 + g;
    uint32_t r0 = pack_bf16(acc[4 * j + 0] * s0, acc[4 * j + 1] * s0);
    uint32_t r1 = pack_bf16(acc[4 * j + 2] * s1, acc[4 * j + 3] * s1);
    uint32_t r2 = pack_bf16(acc[4 * j + 4] * s0, acc[4 * j + 5] * s0);
    uint32_t r3 = pack_bf16(acc[4 * j + 6] * s1, acc[4 * j + 7] * s1);
    const int u = (g & 7) + hi;
    stmatrix_x4(rowaddr + (g >> 3) * 8192 + ((u ^ r7) << 4), r0, r1, r2, r3);
  }
}

__device__ __forceinline__ void pack_p(const float (&S)[32], uint32_t (&P)[16]) {
#pragma unroll
  for (int i = 0; i < 16; i++) P[i] = pack_bf16(S[2 * i], S[2 * i + 1]);
}

template <int R> __device__ __forceinline__ void reg_alloc() { asm volatile("setmaxnreg.inc.sync.aligned.u32 %0;" ::"n"(R)); }
template <int R> __device__ __forceinline__ void reg_dealloc() { asm volatile("setmaxnreg.dec.sync.aligned.u32 %0;" ::"n"(R)); }
constexpr int REG_CONS = 232, REG_PROD = 40;

__device__ __forceinline__ void row_max64(const float (&S)[32], float& x0, float& x1) {
  float a[8], b[8];
#pragma unroll
  for (int j = 0; j < 8; j++) {
    a[j] = fmaxf(S[4 * j], S[4 * j + 1]);
    b[j] = fmaxf(S[4 * j + 2], S[4 * j + 3]);
  }
#pragma unroll
  for (int j = 0; j < 4; j++) {
    a[j] = fmaxf(a[j], a[j + 4]);
    b[j] = fmaxf(b[j], b[j + 4]);
  }
  a[0] = fmaxf(a[0], a[2]); b[0] = fmaxf(b[0], b[2]);
  a[1] = fmaxf(a[1], a[3]); b[1] = fmaxf(b[1], b[3]);
  x0 = fmaxf(a[0], a[1]);
  x1 = fmaxf(b[0], b[1]);
  x0 = fmaxf(x0, __shfl_xor_sync(0xffffffffu, x0, 1));
  x1 = fmaxf(x1, __shfl_xor_sync(0xffffffffu, x1, 1));
  x0 = fmaxf(x0, __shfl_xor_sync(0xffffffffu, x0, 2));
  x1 = fmaxf(x1, __shfl_xor_sync(0xffffffffu, x1, 2));
}

__device__ __forceinline__ uint64_t desc_mn128h(uint32_t u) {
  return desc_make(u + ((4096u >> 4) << 16), DESC_HI_SW128);
}
__device__ __forceinline__ bool mbar_test(uint32_t bar, uint32_t parity) {
  uint32_t ok;
  asm volatile(
      "{\n.reg .pred p;\nmbarrier.test_wait.parity.shared::cta.b64 p, [%1], %2;\nselp.u32 %0, 1, 0, p;\n}\n"
      : "=r"(ok) : "r"(bar), "r"(parity) : "memory");
  return ok != 0;
}
__device__ __forceinline__ void tma_load_3d_mc(uint32_t dst, const CUtensorMap* tm, uint32_t bar, int c0, int c1, int c2,
                                               uint16_t mask) {
  asm volatile(
      "cp.async.bulk.tensor.3d.shared::cluster.global.mbarrier::complete_tx::bytes.multicast::cluster"
      " [%0], [%1, {%3, %4, %5}], [%2], %6;"
      ::"r"(dst), "l"(tm), "r"(bar), "r"(c0), "r"(c1), "r"(c2), "h"(mask) : "memory");
}
__device__ __forceinline__ void tma_store_3d(const CUtensorMap* tm, uint32_t src, int c0, int c1, int c2) {
  asm volatile("cp.async.bulk.tensor.3d.global.shared::cta.bulk_group [%0, {%2, %3, %4}], [%1];"
               ::"l"(tm), "r"(src), "r"(c0), "r"(c1), "r"(c2) : "memory");
}
__device__ __forceinline__ void red_release_gpu(uint32_t* p, uint32_t v) {
  asm volatile("red.release.gpu.global.add.u32 [%0], %1;" ::"l"(p), "r"(v) : "memory");
}
__device__ __forceinline__ void flag_wait(const uint32_t* p, uint32_t target) {
  asm volatile(
      "{\n.reg .pred P1;\n.reg .u32 cnt, v;\n.reg .s32 d;\nmov.u32 cnt, 0;\n"
      "LAB_WAIT:\n"
      "ld.acquire.gpu.global.u32 v, [%0];\n"
      "sub.s32 d, v, %1;\n"
      "setp.ge.s32 P1, d, 0;\n"
      "@P1 bra DONE;\n"
      "add.u32 cnt, cnt, 1;\n"
      "setp.lt.u32 P1, cnt, 8388608;\n"
      "@P1 bra LAB_WAIT;\n"
      "trap;\n"
      "DONE:\n}" ::"l"(p), "r"(target) : "memory");
}
__device__ __forceinline__ void flag_wait_sleep(const uint32_t* p, uint32_t target) {
  asm volatile(
      "{\n.reg .pred P1;\n.reg .u32 cnt, v;\n.reg .s32 d;\nmov.u32 cnt, 0;\n"
      "LAB_WAIT:\n"
      "ld.acquire.gpu.global.u32 v, [%0];\n"
      "sub.s32 d, v, %1;\n"
      "setp.ge.s32 P1, d, 0;\n"
      "@P1 bra DONE;\n"
      "nanosleep.u32 100;\n"
      "add.u32 cnt, cnt, 1;\n"
      "setp.lt.u32 P1, cnt, 8388608;\n"
      "@P1 bra LAB_WAIT;\n"
      "trap;\n"
      "DONE:\n}" ::"l"(p), "r"(target) : "memory");
}
__device__ __forceinline__ void cluster_arrive_relaxed() { asm volatile("barrier.cluster.arrive.relaxed.aligned;" ::: "memory"); }
__device__ __forceinline__ void cluster_wait() { asm volatile("barrier.cluster.wait.aligned;" ::: "memory"); }
__device__ __forceinline__ void st_shared_u32(uint32_t addr, uint32_t v) {
  asm volatile("st.shared.u32 [%0], %1;" ::"r"(addr), "r"(v) : "memory");
}
__device__ __forceinline__ uint32_t ld_shared_u32(uint32_t addr) {
  uint32_t v;
  asm volatile("ld.shared.u32 %0, [%1];" : "=r"(v) : "r"(addr) : "memory");
  return v;
}
__device__ __forceinline__ void fence_proxy_async_global() { asm volatile("fence.proxy.async.global;" ::: "memory"); }
__device__ __forceinline__ void pace(uint32_t cycles) {
  uint32_t t0, t1;
  asm volatile("mov.u32 %0, %%clock;" : "=r"(t0));
  do {
    __nanosleep(64);
    asm volatile("mov.u32 %0, %%clock;" : "=r"(t1));
  } while (t1 - t0 < cycles);
}

__device__ __forceinline__ void red_relaxed_gpu(uint32_t* p, uint32_t v) {
  asm volatile("red.relaxed.gpu.global.add.u32 [%0], %1;" ::"l"(p), "r"(v) : "memory");
}
__device__ __forceinline__ float rcp_fast(float x) {
  float r;
  asm("rcp.approx.ftz.f32 %0, %1;" : "=f"(r) : "f"(x));
  return r;
}

__device__ __forceinline__ void wgmma_ss_n256_t(float (&d)[128], uint64_t da, uint64_t db, int sd) {
  asm volatile("{\n.reg .pred p;\nsetp.ne.b32 p, %130, 0;\n"
    "wgmma.mma_async.sync.aligned.m64n256k16.f32.bf16.bf16 "
    "{%0,%1,%2,%3,%4,%5,%6,%7,%8,%9,%10,%11,%12,%13,%14,%15,%16,%17,%18,%19,%20,%21,%22,%23,%24,%25,%26,%27,%28,%29,%30,%31,%32,%33,%34,%35,%36,%37,%38,%39,%40,%41,%42,%43,%44,%45,%46,%47,%48,%49,%50,%51,%52,%53,%54,%55,%56,%57,%58,%59,%60,%61,%62,%63,%64,%65,%66,%67,%68,%69,%70,%71,%72,%73,%74,%75,%76,%77,%78,%79,%80,%81,%82,%83,%84,%85,%86,%87,%88,%89,%90,%91,%92,%93,%94,%95,%96,%97,%98,%99,%100,%101,%102,%103,%104,%105,%106,%107,%108,%109,%110,%111,%112,%113,%114,%115,%116,%117,%118,%119,%120,%121,%122,%123,%124,%125,%126,%127}, %128, %129, p, 1, 1, 0, 1;\n}\n"
    : "+f"(d[0]),"+f"(d[1]),"+f"(d[2]),"+f"(d[3]),"+f"(d[4]),"+f"(d[5]),"+f"(d[6]),"+f"(d[7]),"+f"(d[8]),"+f"(d[9]),"+f"(d[10]),"+f"(d[11]),"+f"(d[12]),"+f"(d[13]),"+f"(d[14]),"+f"(d[15]),"+f"(d[16]),"+f"(d[17]),"+f"(d[18]),"+f"(d[19]),"+f"(d[20]),"+f"(d[21]),"+f"(d[22]),"+f"(d[23]),"+f"(d[24]),"+f"(d[25]),"+f"(d[26]),"+f"(d[27]),"+f"(d[28]),"+f"(d[29]),"+f"(d[30]),"+f"(d[31]),"+f"(d[32]),"+f"(d[33]),"+f"(d[34]),"+f"(d[35]),"+f"(d[36]),"+f"(d[37]),"+f"(d[38]),"+f"(d[39]),"+f"(d[40]),"+f"(d[41]),"+f"(d[42]),"+f"(d[43]),"+f"(d[44]),"+f"(d[45]),"+f"(d[46]),"+f"(d[47]),"+f"(d[48]),"+f"(d[49]),"+f"(d[50]),"+f"(d[51]),"+f"(d[52]),"+f"(d[53]),"+f"(d[54]),"+f"(d[55]),"+f"(d[56]),"+f"(d[57]),"+f"(d[58]),"+f"(d[59]),"+f"(d[60]),"+f"(d[61]),"+f"(d[62]),"+f"(d[63]),"+f"(d[64]),"+f"(d[65]),"+f"(d[66]),"+f"(d[67]),"+f"(d[68]),"+f"(d[69]),"+f"(d[70]),"+f"(d[71]),"+f"(d[72]),"+f"(d[73]),"+f"(d[74]),"+f"(d[75]),"+f"(d[76]),"+f"(d[77]),"+f"(d[78]),"+f"(d[79]),"+f"(d[80]),"+f"(d[81]),"+f"(d[82]),"+f"(d[83]),"+f"(d[84]),"+f"(d[85]),"+f"(d[86]),"+f"(d[87]),"+f"(d[88]),"+f"(d[89]),"+f"(d[90]),"+f"(d[91]),"+f"(d[92]),"+f"(d[93]),"+f"(d[94]),"+f"(d[95]),"+f"(d[96]),"+f"(d[97]),"+f"(d[98]),"+f"(d[99]),"+f"(d[100]),"+f"(d[101]),"+f"(d[102]),"+f"(d[103]),"+f"(d[104]),"+f"(d[105]),"+f"(d[106]),"+f"(d[107]),"+f"(d[108]),"+f"(d[109]),"+f"(d[110]),"+f"(d[111]),"+f"(d[112]),"+f"(d[113]),"+f"(d[114]),"+f"(d[115]),"+f"(d[116]),"+f"(d[117]),"+f"(d[118]),"+f"(d[119]),"+f"(d[120]),"+f"(d[121]),"+f"(d[122]),"+f"(d[123]),"+f"(d[124]),"+f"(d[125]),"+f"(d[126]),"+f"(d[127])
    : "l"(da), "l"(db), "r"(sd));
}
__device__ __forceinline__ void wgmma_rs_n256_t(float (&d)[128], uint32_t a0, uint32_t a1, uint32_t a2, uint32_t a3, uint64_t db, int sd) {
  asm volatile("{\n.reg .pred p;\nsetp.ne.b32 p, %133, 0;\n"
    "wgmma.mma_async.sync.aligned.m64n256k16.f32.bf16.bf16 "
    "{%0,%1,%2,%3,%4,%5,%6,%7,%8,%9,%10,%11,%12,%13,%14,%15,%16,%17,%18,%19,%20,%21,%22,%23,%24,%25,%26,%27,%28,%29,%30,%31,%32,%33,%34,%35,%36,%37,%38,%39,%40,%41,%42,%43,%44,%45,%46,%47,%48,%49,%50,%51,%52,%53,%54,%55,%56,%57,%58,%59,%60,%61,%62,%63,%64,%65,%66,%67,%68,%69,%70,%71,%72,%73,%74,%75,%76,%77,%78,%79,%80,%81,%82,%83,%84,%85,%86,%87,%88,%89,%90,%91,%92,%93,%94,%95,%96,%97,%98,%99,%100,%101,%102,%103,%104,%105,%106,%107,%108,%109,%110,%111,%112,%113,%114,%115,%116,%117,%118,%119,%120,%121,%122,%123,%124,%125,%126,%127}, {%128,%129,%130,%131}, %132, p, 1, 1, 1;\n}\n"
    : "+f"(d[0]),"+f"(d[1]),"+f"(d[2]),"+f"(d[3]),"+f"(d[4]),"+f"(d[5]),"+f"(d[6]),"+f"(d[7]),"+f"(d[8]),"+f"(d[9]),"+f"(d[10]),"+f"(d[11]),"+f"(d[12]),"+f"(d[13]),"+f"(d[14]),"+f"(d[15]),"+f"(d[16]),"+f"(d[17]),"+f"(d[18]),"+f"(d[19]),"+f"(d[20]),"+f"(d[21]),"+f"(d[22]),"+f"(d[23]),"+f"(d[24]),"+f"(d[25]),"+f"(d[26]),"+f"(d[27]),"+f"(d[28]),"+f"(d[29]),"+f"(d[30]),"+f"(d[31]),"+f"(d[32]),"+f"(d[33]),"+f"(d[34]),"+f"(d[35]),"+f"(d[36]),"+f"(d[37]),"+f"(d[38]),"+f"(d[39]),"+f"(d[40]),"+f"(d[41]),"+f"(d[42]),"+f"(d[43]),"+f"(d[44]),"+f"(d[45]),"+f"(d[46]),"+f"(d[47]),"+f"(d[48]),"+f"(d[49]),"+f"(d[50]),"+f"(d[51]),"+f"(d[52]),"+f"(d[53]),"+f"(d[54]),"+f"(d[55]),"+f"(d[56]),"+f"(d[57]),"+f"(d[58]),"+f"(d[59]),"+f"(d[60]),"+f"(d[61]),"+f"(d[62]),"+f"(d[63]),"+f"(d[64]),"+f"(d[65]),"+f"(d[66]),"+f"(d[67]),"+f"(d[68]),"+f"(d[69]),"+f"(d[70]),"+f"(d[71]),"+f"(d[72]),"+f"(d[73]),"+f"(d[74]),"+f"(d[75]),"+f"(d[76]),"+f"(d[77]),"+f"(d[78]),"+f"(d[79]),"+f"(d[80]),"+f"(d[81]),"+f"(d[82]),"+f"(d[83]),"+f"(d[84]),"+f"(d[85]),"+f"(d[86]),"+f"(d[87]),"+f"(d[88]),"+f"(d[89]),"+f"(d[90]),"+f"(d[91]),"+f"(d[92]),"+f"(d[93]),"+f"(d[94]),"+f"(d[95]),"+f"(d[96]),"+f"(d[97]),"+f"(d[98]),"+f"(d[99]),"+f"(d[100]),"+f"(d[101]),"+f"(d[102]),"+f"(d[103]),"+f"(d[104]),"+f"(d[105]),"+f"(d[106]),"+f"(d[107]),"+f"(d[108]),"+f"(d[109]),"+f"(d[110]),"+f"(d[111]),"+f"(d[112]),"+f"(d[113]),"+f"(d[114]),"+f"(d[115]),"+f"(d[116]),"+f"(d[117]),"+f"(d[118]),"+f"(d[119]),"+f"(d[120]),"+f"(d[121]),"+f"(d[122]),"+f"(d[123]),"+f"(d[124]),"+f"(d[125]),"+f"(d[126]),"+f"(d[127])
    : "r"(a0), "r"(a1), "r"(a2), "r"(a3), "l"(db), "r"(sd));
}
__device__ __forceinline__ void wgmma_ss_n224_t(float (&d)[112], uint64_t da, uint64_t db, int sd) {
  asm volatile("{\n.reg .pred p;\nsetp.ne.b32 p, %114, 0;\n"
    "wgmma.mma_async.sync.aligned.m64n224k16.f32.bf16.bf16 "
    "{%0,%1,%2,%3,%4,%5,%6,%7,%8,%9,%10,%11,%12,%13,%14,%15,%16,%17,%18,%19,%20,%21,%22,%23,%24,%25,%26,%27,%28,%29,%30,%31,%32,%33,%34,%35,%36,%37,%38,%39,%40,%41,%42,%43,%44,%45,%46,%47,%48,%49,%50,%51,%52,%53,%54,%55,%56,%57,%58,%59,%60,%61,%62,%63,%64,%65,%66,%67,%68,%69,%70,%71,%72,%73,%74,%75,%76,%77,%78,%79,%80,%81,%82,%83,%84,%85,%86,%87,%88,%89,%90,%91,%92,%93,%94,%95,%96,%97,%98,%99,%100,%101,%102,%103,%104,%105,%106,%107,%108,%109,%110,%111}, %112, %113, p, 1, 1, 0, 1;\n}\n"
    : "+f"(d[0]),"+f"(d[1]),"+f"(d[2]),"+f"(d[3]),"+f"(d[4]),"+f"(d[5]),"+f"(d[6]),"+f"(d[7]),"+f"(d[8]),"+f"(d[9]),"+f"(d[10]),"+f"(d[11]),"+f"(d[12]),"+f"(d[13]),"+f"(d[14]),"+f"(d[15]),"+f"(d[16]),"+f"(d[17]),"+f"(d[18]),"+f"(d[19]),"+f"(d[20]),"+f"(d[21]),"+f"(d[22]),"+f"(d[23]),"+f"(d[24]),"+f"(d[25]),"+f"(d[26]),"+f"(d[27]),"+f"(d[28]),"+f"(d[29]),"+f"(d[30]),"+f"(d[31]),"+f"(d[32]),"+f"(d[33]),"+f"(d[34]),"+f"(d[35]),"+f"(d[36]),"+f"(d[37]),"+f"(d[38]),"+f"(d[39]),"+f"(d[40]),"+f"(d[41]),"+f"(d[42]),"+f"(d[43]),"+f"(d[44]),"+f"(d[45]),"+f"(d[46]),"+f"(d[47]),"+f"(d[48]),"+f"(d[49]),"+f"(d[50]),"+f"(d[51]),"+f"(d[52]),"+f"(d[53]),"+f"(d[54]),"+f"(d[55]),"+f"(d[56]),"+f"(d[57]),"+f"(d[58]),"+f"(d[59]),"+f"(d[60]),"+f"(d[61]),"+f"(d[62]),"+f"(d[63]),"+f"(d[64]),"+f"(d[65]),"+f"(d[66]),"+f"(d[67]),"+f"(d[68]),"+f"(d[69]),"+f"(d[70]),"+f"(d[71]),"+f"(d[72]),"+f"(d[73]),"+f"(d[74]),"+f"(d[75]),"+f"(d[76]),"+f"(d[77]),"+f"(d[78]),"+f"(d[79]),"+f"(d[80]),"+f"(d[81]),"+f"(d[82]),"+f"(d[83]),"+f"(d[84]),"+f"(d[85]),"+f"(d[86]),"+f"(d[87]),"+f"(d[88]),"+f"(d[89]),"+f"(d[90]),"+f"(d[91]),"+f"(d[92]),"+f"(d[93]),"+f"(d[94]),"+f"(d[95]),"+f"(d[96]),"+f"(d[97]),"+f"(d[98]),"+f"(d[99]),"+f"(d[100]),"+f"(d[101]),"+f"(d[102]),"+f"(d[103]),"+f"(d[104]),"+f"(d[105]),"+f"(d[106]),"+f"(d[107]),"+f"(d[108]),"+f"(d[109]),"+f"(d[110]),"+f"(d[111])
    : "l"(da), "l"(db), "r"(sd));
}
__device__ __forceinline__ void wgmma_ss_n168_t(float (&d)[84], uint64_t da, uint64_t db, int sd) {
  asm volatile("{\n.reg .pred p;\nsetp.ne.b32 p, %86, 0;\n"
    "wgmma.mma_async.sync.aligned.m64n168k16.f32.bf16.bf16 "
    "{%0,%1,%2,%3,%4,%5,%6,%7,%8,%9,%10,%11,%12,%13,%14,%15,%16,%17,%18,%19,%20,%21,%22,%23,%24,%25,%26,%27,%28,%29,%30,%31,%32,%33,%34,%35,%36,%37,%38,%39,%40,%41,%42,%43,%44,%45,%46,%47,%48,%49,%50,%51,%52,%53,%54,%55,%56,%57,%58,%59,%60,%61,%62,%63,%64,%65,%66,%67,%68,%69,%70,%71,%72,%73,%74,%75,%76,%77,%78,%79,%80,%81,%82,%83}, %84, %85, p, 1, 1, 0, 1;\n}\n"
    : "+f"(d[0]),"+f"(d[1]),"+f"(d[2]),"+f"(d[3]),"+f"(d[4]),"+f"(d[5]),"+f"(d[6]),"+f"(d[7]),"+f"(d[8]),"+f"(d[9]),"+f"(d[10]),"+f"(d[11]),"+f"(d[12]),"+f"(d[13]),"+f"(d[14]),"+f"(d[15]),"+f"(d[16]),"+f"(d[17]),"+f"(d[18]),"+f"(d[19]),"+f"(d[20]),"+f"(d[21]),"+f"(d[22]),"+f"(d[23]),"+f"(d[24]),"+f"(d[25]),"+f"(d[26]),"+f"(d[27]),"+f"(d[28]),"+f"(d[29]),"+f"(d[30]),"+f"(d[31]),"+f"(d[32]),"+f"(d[33]),"+f"(d[34]),"+f"(d[35]),"+f"(d[36]),"+f"(d[37]),"+f"(d[38]),"+f"(d[39]),"+f"(d[40]),"+f"(d[41]),"+f"(d[42]),"+f"(d[43]),"+f"(d[44]),"+f"(d[45]),"+f"(d[46]),"+f"(d[47]),"+f"(d[48]),"+f"(d[49]),"+f"(d[50]),"+f"(d[51]),"+f"(d[52]),"+f"(d[53]),"+f"(d[54]),"+f"(d[55]),"+f"(d[56]),"+f"(d[57]),"+f"(d[58]),"+f"(d[59]),"+f"(d[60]),"+f"(d[61]),"+f"(d[62]),"+f"(d[63]),"+f"(d[64]),"+f"(d[65]),"+f"(d[66]),"+f"(d[67]),"+f"(d[68]),"+f"(d[69]),"+f"(d[70]),"+f"(d[71]),"+f"(d[72]),"+f"(d[73]),"+f"(d[74]),"+f"(d[75]),"+f"(d[76]),"+f"(d[77]),"+f"(d[78]),"+f"(d[79]),"+f"(d[80]),"+f"(d[81]),"+f"(d[82]),"+f"(d[83])
    : "l"(da), "l"(db), "r"(sd));
}
__device__ __forceinline__ void wgmma_ss_n64(float (&d)[32], uint64_t da, uint64_t db, int sd) {
  asm volatile("{\n.reg .pred p;\nsetp.ne.b32 p, %34, 0;\n"
    "wgmma.mma_async.sync.aligned.m64n64k16.f32.bf16.bf16 "
    "{%0,%1,%2,%3,%4,%5,%6,%7,%8,%9,%10,%11,%12,%13,%14,%15,%16,%17,%18,%19,%20,%21,%22,%23,%24,%25,%26,%27,%28,%29,%30,%31}, %32, %33, p, 1, 1, 0, 0;\n}\n"
    : "+f"(d[0]),"+f"(d[1]),"+f"(d[2]),"+f"(d[3]),"+f"(d[4]),"+f"(d[5]),"+f"(d[6]),"+f"(d[7]),"+f"(d[8]),"+f"(d[9]),"+f"(d[10]),"+f"(d[11]),"+f"(d[12]),"+f"(d[13]),"+f"(d[14]),"+f"(d[15]),"+f"(d[16]),"+f"(d[17]),"+f"(d[18]),"+f"(d[19]),"+f"(d[20]),"+f"(d[21]),"+f"(d[22]),"+f"(d[23]),"+f"(d[24]),"+f"(d[25]),"+f"(d[26]),"+f"(d[27]),"+f"(d[28]),"+f"(d[29]),"+f"(d[30]),"+f"(d[31])
    : "l"(da), "l"(db), "r"(sd));
}
__device__ __forceinline__ void wgmma_rs_n64(float (&d)[32], uint32_t a0, uint32_t a1, uint32_t a2, uint32_t a3, uint64_t db, int sd) {
  asm volatile("{\n.reg .pred p;\nsetp.ne.b32 p, %37, 0;\n"
    "wgmma.mma_async.sync.aligned.m64n64k16.f32.bf16.bf16 "
    "{%0,%1,%2,%3,%4,%5,%6,%7,%8,%9,%10,%11,%12,%13,%14,%15,%16,%17,%18,%19,%20,%21,%22,%23,%24,%25,%26,%27,%28,%29,%30,%31}, {%32,%33,%34,%35}, %36, p, 1, 1, 0;\n}\n"
    : "+f"(d[0]),"+f"(d[1]),"+f"(d[2]),"+f"(d[3]),"+f"(d[4]),"+f"(d[5]),"+f"(d[6]),"+f"(d[7]),"+f"(d[8]),"+f"(d[9]),"+f"(d[10]),"+f"(d[11]),"+f"(d[12]),"+f"(d[13]),"+f"(d[14]),"+f"(d[15]),"+f"(d[16]),"+f"(d[17]),"+f"(d[18]),"+f"(d[19]),"+f"(d[20]),"+f"(d[21]),"+f"(d[22]),"+f"(d[23]),"+f"(d[24]),"+f"(d[25]),"+f"(d[26]),"+f"(d[27]),"+f"(d[28]),"+f"(d[29]),"+f"(d[30]),"+f"(d[31])
    : "r"(a0), "r"(a1), "r"(a2), "r"(a3), "l"(db), "r"(sd));
}
__device__ __forceinline__ void wgmma_rs_n32_t(float (&d)[16], uint32_t a0, uint32_t a1, uint32_t a2, uint32_t a3, uint64_t db, int sd) {
  asm volatile("{\n.reg .pred p;\nsetp.ne.b32 p, %21, 0;\n"
    "wgmma.mma_async.sync.aligned.m64n32k16.f32.bf16.bf16 "
    "{%0,%1,%2,%3,%4,%5,%6,%7,%8,%9,%10,%11,%12,%13,%14,%15}, {%16,%17,%18,%19}, %20, p, 1, 1, 1;\n}\n"
    : "+f"(d[0]),"+f"(d[1]),"+f"(d[2]),"+f"(d[3]),"+f"(d[4]),"+f"(d[5]),"+f"(d[6]),"+f"(d[7]),"+f"(d[8]),"+f"(d[9]),"+f"(d[10]),"+f"(d[11]),"+f"(d[12]),"+f"(d[13]),"+f"(d[14]),"+f"(d[15])
    : "r"(a0), "r"(a1), "r"(a2), "r"(a3), "l"(db), "r"(sd));
}

namespace mk {
constexpr uint32_t NU = 10;
constexpr uint32_t UNIT = 16384;
constexpr uint32_t OFF_RING = 65536;
constexpr uint32_t OFF_BAR = OFF_RING + NU * UNIT;
constexpr uint32_t NU1 = 9;
constexpr uint32_t OFF_AK = OFF_RING + 9 * UNIT, OFF_AV = OFF_AK + 8192;
constexpr uint32_t B_FULL = 0, B_EMPTY = 64, B_AF = 128, B_AE = 144, B_FA = 160, B_EP = 176, B_STRDY = 192,
                   B_STFREE = 208, S_EPOCH = 224, B_CX = 232;
constexpr uint32_t SMEM = OFF_BAR + 320 + 1024;
constexpr int NCTA = 132;
constexpr uint32_t STORE_GAP = 1700, CTX0_GAP = 1000, CTX1_GAP = 300;
constexpr int DA = 6;
constexpr int F_TICKET = 0, F_A = 32, F_OA = 64, F_KV = 128, F_CTX = 256, F_X = 384, F_COUNT = 512;
constexpr float SC_A = 0.18898223650461361f * 1.4426950408889634f;
constexpr float SC_B = 0.0625f * 1.4426950408889634f;
constexpr float LAZY_TAU = 8.0f;
constexpr int BAR_WG0 = 1;

__device__ __forceinline__ uint32_t unit_add(uint32_t u, uint32_t k, uint32_t nu) {
  u += k;
  return u >= nu ? u - nu : u;
}
}

extern __shared__ uint8_t smem_raw[];

struct Params {
  CUtensorMap xA, wqkv, qkvA, c, wuk3, wuv3, kv3, kv_st1, v3, xB, wq3, ctx, woB, woA, oA, outB, outA;
  const bf16* qkvA_p;
  bf16* oA_p;
  float4* part;
  uint32_t* flags;
};

struct Ids {
  int cl, wg, wq, lane;
  uint32_t rank, sbase;
};
__device__ __forceinline__ Ids make_ids() {
  Ids d;
  uint32_t tid, cta, sm;
  asm volatile("mov.u32 %0, %%tid.x;" : "=r"(tid));
  asm volatile("mov.u32 %0, %%ctaid.x;" : "=r"(cta));
  asm volatile("mov.u32 %0, %%cluster_ctarank;" : "=r"(d.rank));
  asm volatile("mov.u32 %0, smem_raw;" : "=r"(sm));
  const int warp = __shfl_sync(0xffffffffu, tid >> 5, 0);
  d.cl = cta >> 1;
  d.wg = warp >> 2;
  d.wq = warp & 3;
  d.lane = tid & 31;
  d.sbase = (sm + 1023u) & ~1023u;
  return d;
}

struct ProdRing {
  uint32_t g = 0, u = 0, tail = 0, free_units = mk::NU1, lens = 0, nu = mk::NU1;
  uint32_t bar, ring;
  __device__ __forceinline__ uint32_t acquire(uint32_t len, uint32_t bytes, uint32_t extra = 0) {
    const uint32_t fb = bar + mk::B_FULL + (g & 7) * 8;
    mbar_expect_tx(fb, bytes);
    while (free_units < len) {
      mbar_wait(bar + mk::B_EMPTY + (tail & 7) * 8, (tail >> 3) & 1);
      free_units += (lens >> ((tail & 7) * 4)) & 15;
      tail++;
    }
    free_units -= len;
    lens = (lens & ~(15u << ((g & 7) * 4))) | ((len + extra) << ((g & 7) * 4));
    return fb;
  }
  __device__ __forceinline__ uint32_t unit(uint32_t k) const { return ring + mk::unit_add(u, k, nu) * mk::UNIT; }
  __device__ __forceinline__ void next(uint32_t len) {
    g++;
    u = mk::unit_add(u, len, nu);
  }
};

struct Cons {
  uint32_t g, cur;
  uint32_t bar, ring16, last16;
  uint32_t rel;
  bool rel_thread;
  __device__ __forceinline__ uint32_t full(uint32_t gg) const { return bar + mk::B_FULL + (gg & 7) * 8; }
  __device__ __forceinline__ void wait(uint32_t gg) const { mbar_wait(full(gg), (gg >> 3) & 1); }
  __device__ __forceinline__ bool test(uint32_t gg) const { return mbar_test(full(gg), (gg >> 3) & 1); }
  __device__ __forceinline__ void release(uint32_t gg) const {
    if (rel_thread) mbar_arrive_cluster(rel + (gg & 7) * 8);
  }
  __device__ __forceinline__ uint32_t adv(uint32_t x) const { return x == last16 ? ring16 : x + (mk::UNIT >> 4); }
};

__device__ __forceinline__ void issue_gemm256(float (&acc)[128], const Cons& c, int wg, int first) {
  const uint32_t xa = c.cur + wg * 512;
  const uint32_t w0 = c.adv(c.cur), w1 = c.adv(w0);
  wgmma_ss_n256_t(acc, desc_k128(xa), desc_mn128h(w0), !first);
  wgmma_ss_n256_t(acc, desc_k128(xa + 2), desc_mn128h(w0 + 128), 1);
  wgmma_ss_n256_t(acc, desc_k128(xa + 4), desc_mn128h(w1), 1);
  wgmma_ss_n256_t(acc, desc_k128(xa + 6), desc_mn128h(w1 + 128), 1);
}
__device__ __forceinline__ void issue_gemm256c(float (&acc)[128], uint32_t ub, int wg, int first) {
  const uint32_t xa = ub + wg * 512;
  wgmma_ss_n256_t(acc, desc_k128(xa), desc_mn128h(ub + 1024), !first);
  wgmma_ss_n256_t(acc, desc_k128(xa + 2), desc_mn128h(ub + 1024 + 128), 1);
  wgmma_ss_n256_t(acc, desc_k128(xa + 4), desc_mn128h(ub + 2048), 1);
  wgmma_ss_n256_t(acc, desc_k128(xa + 6), desc_mn128h(ub + 2048 + 128), 1);
}
template <int N>
__device__ __forceinline__ void issue_gemm_n(float (&acc)[N / 2], const Cons& c, int wg, int first) {
  const uint32_t xa = c.cur + wg * 512;
  const uint32_t w0 = c.adv(c.cur), w1 = c.adv(w0);
  if constexpr (N == 168) {
    wgmma_ss_n168_t(acc, desc_k128(xa), desc_mn128h(w0), !first);
    wgmma_ss_n168_t(acc, desc_k128(xa + 2), desc_mn128h(w0 + 128), 1);
    wgmma_ss_n168_t(acc, desc_k128(xa + 4), desc_mn128h(w1), 1);
    wgmma_ss_n168_t(acc, desc_k128(xa + 6), desc_mn128h(w1 + 128), 1);
  } else {
    wgmma_ss_n224_t(acc, desc_k128(xa), desc_mn128h(w0), !first);
    wgmma_ss_n224_t(acc, desc_k128(xa + 2), desc_mn128h(w0 + 128), 1);
    wgmma_ss_n224_t(acc, desc_k128(xa + 4), desc_mn128h(w1), 1);
    wgmma_ss_n224_t(acc, desc_k128(xa + 6), desc_mn128h(w1 + 128), 1);
  }
}
template <int N>
__device__ __forceinline__ void gemm_loop(float (&acc)[N / 2], Cons& c, int wg, int nkb) {
  bool ok = false;
#pragma unroll 1
  for (int kb = 0; kb < nkb; kb++) {
    if (!ok) c.wait(c.g);
    reg_fence(acc);
    wg_fence();
    if constexpr (N == 256) issue_gemm256(acc, c, wg, kb == 0);
    else issue_gemm_n<N>(acc, c, wg, kb == 0);
    wg_commit();
    if (kb > 0) {
      wg_wait<1>();
      c.release(c.g - 1);
    }
    ok = c.test(c.g + 1);
    c.g++;
    c.cur = c.adv(c.adv(c.adv(c.cur)));
  }
  wg_wait<0>();
  reg_fence(acc);
  c.release(c.g - 1);
}

struct StoreCtl {
  uint32_t rdy, fre, jobs;
  __device__ __forceinline__ void wait_free() const {
    if (jobs > 0) mbar_wait(fre, (jobs - 1) & 1);
  }
  __device__ __forceinline__ void submit(int lane) {
    fence_proxy_async();
    __syncwarp();
    if (lane == 0) mbar_arrive(rdy);
    jobs++;
  }
  __device__ __forceinline__ void signal(int lane) {
    __syncwarp();
    if (lane == 0) mbar_arrive(rdy);
    jobs++;
  }
};

__device__ __forceinline__ void causal_mask(float (&S)[32], int wq, int lane) {
  const int r0 = wq * 16 + (lane >> 2);
  const int cb = (lane & 3) * 2;
#pragma unroll
  for (int j = 0; j < 8; j++) {
    const int c = 8 * j + cb;
    if (c > r0) S[4 * j + 0] = -INFINITY;
    if (c + 1 > r0) S[4 * j + 1] = -INFINITY;
    if (c > r0 + 8) S[4 * j + 2] = -INFINITY;
    if (c + 1 > r0 + 8) S[4 * j + 3] = -INFINITY;
  }
}

__device__ __forceinline__ bool softmax_b(float (&S)[32], float& m0, float& m1, float& l0, float& l1, float& a0,
                                          float& a1) {
  float x0, x1;
  row_max64(S, x0, x1);
  const bool need = ((x0 - m0) * mk::SC_B > mk::LAZY_TAU) || ((x1 - m1) * mk::SC_B > mk::LAZY_TAU);
  const bool upd = __any_sync(0xffffffffu, need);
  a0 = 1.f;
  a1 = 1.f;
  if (upd) {
    const float n0 = fmaxf(m0, x0), n1 = fmaxf(m1, x1);
    a0 = ex2((m0 - n0) * mk::SC_B);
    a1 = ex2((m1 - n1) * mk::SC_B);
    m0 = n0;
    m1 = n1;
  }
  const float c0 = m0 * mk::SC_B, c1 = m1 * mk::SC_B;
  float s0 = 0.f, s1 = 0.f, s2 = 0.f, s3 = 0.f;
#pragma unroll
  for (int j = 0; j < 8; j++) {
    S[4 * j + 0] = ex2(fmaf(S[4 * j + 0], mk::SC_B, -c0));
    S[4 * j + 1] = ex2(fmaf(S[4 * j + 1], mk::SC_B, -c0));
    S[4 * j + 2] = ex2(fmaf(S[4 * j + 2], mk::SC_B, -c1));
    S[4 * j + 3] = ex2(fmaf(S[4 * j + 3], mk::SC_B, -c1));
    s0 += S[4 * j + 0];
    s1 += S[4 * j + 1];
    s2 += S[4 * j + 2];
    s3 += S[4 * j + 3];
  }
  l0 = fmaf(l0, a0, s0 + s1);
  l1 = fmaf(l1, a1, s2 + s3);
  return upd;
}

__device__ __forceinline__ void issue_qk_b(float (&S)[32], uint32_t q16, uint32_t k0, uint32_t k1) {
#pragma unroll
  for (int ks = 0; ks < 16; ks++) {
    const uint32_t off = ((ks >> 2) & 1) * 512 + (ks & 3) * 2;
    wgmma_ss_n64(S, desc_k128(q16 + (ks >> 2) * 512 + (ks & 3) * 2), desc_k128((ks < 8 ? k0 : k1) + off), ks != 0);
  }
}
__device__ __forceinline__ void issue_pv_b(float (&O)[128], const uint32_t (&P)[16], uint32_t v0, uint32_t v1, int accumulate) {
  wgmma_rs_n256_t(O, P[0], P[1], P[2], P[3], desc_mn128h(v0), accumulate);
  wgmma_rs_n256_t(O, P[4], P[5], P[6], P[7], desc_mn128h(v0 + 128), 1);
  wgmma_rs_n256_t(O, P[8], P[9], P[10], P[11], desc_mn128h(v1), 1);
  wgmma_rs_n256_t(O, P[12], P[13], P[14], P[15], desc_mn128h(v1 + 128), 1);
}

__device__ __forceinline__ void attention_b_tile(float (&O)[128], float (&S)[32], uint32_t (&P)[16], Cons& c, StoreCtl& st,
                                                 uint32_t priv, int wg, int wq, int lane, int tile, int m,
                                                 uint32_t rank) {
  using namespace mk;
  const int N = 4 * m + 4;
  const bool is_long = (wg == tile);
  const int g = is_long ? (rank == 0 ? 3 : 2) : (rank == 0 ? 0 : 1);
  const int n = 4 * m + g + 1;
  const uint32_t q16 = a16(priv);

  st.wait_free();
  store_acc_sw128<0, 32, 128>(O, priv, wq, lane, 1.f, 1.f);
  fence_proxy_async();
  named_bar_sync(BAR_WG0 + wg, 128);

  float m0 = -INFINITY, m1 = -INFINITY, l0 = 0.f, l1 = 0.f, a0, a1;
  {
    c.wait(c.g);
    wg_fence();
    issue_qk_b(S, q16, c.cur, c.adv(c.cur));
    wg_commit();
    wg_wait<0>();
    reg_fence(S);
    c.release(c.g);
    c.g++;
    c.cur = c.adv(c.adv(c.cur));
    if (n == 1) causal_mask(S, wq, lane);
    softmax_b(S, m0, m1, l0, l1, a0, a1);
    pack_p(S, P);
  }
  bool ok_k = false, ok_v = false;
#pragma unroll 1
  for (int j = 1; j < n; j++) {
    if (!ok_k) c.wait(c.g);
    if (!ok_v) c.wait(c.g + 1);
    const uint32_t k0 = c.cur, k1 = c.adv(k0), v0 = c.adv(k1), v1 = c.adv(v0);
    reg_fence(O);
    reg_fence(P);
    wg_fence();
    issue_qk_b(S, q16, k0, k1);
    wg_commit();
    issue_pv_b(O, P, v0, v1, j != 1);
    wg_commit();
    ok_k = c.test(c.g + 2);
    ok_v = c.test(c.g + 3);
    wg_wait<1>();
    reg_fence(S);
    c.release(c.g);
    if (j == n - 1) causal_mask(S, wq, lane);
    const bool upd = softmax_b(S, m0, m1, l0, l1, a0, a1);
    wg_wait<0>();
    reg_fence(O);
    reg_fence(P);
    c.release(c.g + 1);
    pack_p(S, P);
    if (upd) {
#pragma unroll
      for (int i = 0; i < 32; i++) {
        O[4 * i + 0] *= a0;
        O[4 * i + 1] *= a0;
        O[4 * i + 2] *= a1;
        O[4 * i + 3] *= a1;
      }
    }
    c.g += 2;
    c.cur = c.adv(v1);
  }
  if (n < N) {
    c.wait(c.g);
    c.release(c.g);
    c.g++;
    c.cur = c.adv(c.adv(c.cur));
  }
  {
    c.wait(c.g);
    reg_fence(O);
    reg_fence(P);
    wg_fence();
    issue_pv_b(O, P, c.cur, c.adv(c.cur), n != 1);
    wg_commit();
    wg_wait<0>();
    reg_fence(O);
    c.release(c.g);
    c.g++;
    c.cur = c.adv(c.adv(c.cur));
  }
  l0 += __shfl_xor_sync(0xffffffffu, l0, 1);
  l1 += __shfl_xor_sync(0xffffffffu, l1, 1);
  l0 += __shfl_xor_sync(0xffffffffu, l0, 2);
  l1 += __shfl_xor_sync(0xffffffffu, l1, 2);
  store_acc_sw128<0, 32, 128>(O, priv, wq, lane, rcp_fast(l0), rcp_fast(l1));
  st.submit(lane);
  if (n < N) {
    const int rest = 2 * (N - 1 - n) + 1;
    for (int s = 0; s < rest; s++) {
      c.wait(c.g);
      c.release(c.g);
      c.g++;
      c.cur = c.adv(c.adv(c.cur));
    }
  }
}

struct AttnA {
  float O[16];
  uint32_t Q[8];
};

__global__ void __cluster_dims__(2, 1, 1) __launch_bounds__(384, 1) k_mega(const __grid_constant__ Params p) {
  using namespace mk;
  const uint32_t sbase = (smem_u32(smem_raw) + 1023u) & ~1023u;
  const uint32_t bar = sbase + OFF_BAR;
  const int warp = __shfl_sync(0xffffffffu, threadIdx.x >> 5, 0);
  const int lane = threadIdx.x & 31;
  const uint32_t rank = cluster_ctarank();
  const int cl = blockIdx.x >> 1;
  const bool main_cl = cl < 64;

  if (threadIdx.x == 0) {
    for (int i = 0; i < 8; i++) {
      mbar_init(bar + B_FULL + i * 8, 1);
      mbar_init(bar + B_EMPTY + i * 8, 4);
    }
    for (int i = 0; i < 4; i++) mbar_init(bar + B_CX + i * 8, 1);
    for (int i = 0; i < 2; i++) {
      mbar_init(bar + B_AF + i * 8, 1);
      mbar_init(bar + B_AE + i * 8, 4);
      mbar_init(bar + B_FA + i * 8, 1);
      mbar_init(bar + B_EP + i * 8, 1);
      mbar_init(bar + B_STRDY + i * 8, 4);
      mbar_init(bar + B_STFREE + i * 8, 1);
    }
    fence_barrier_init();
  } else if (threadIdx.x == 256) {
    tma_prefetch_desc(&p.xA); tma_prefetch_desc(&p.wqkv);
  } else if (threadIdx.x == 288) {
    tma_prefetch_desc(&p.c); tma_prefetch_desc(&p.wuk3); tma_prefetch_desc(&p.qkvA);
  }
  __syncthreads();
  cluster_arrive_relaxed();
  cluster_wait();
  if (threadIdx.x == 256 && main_cl) {
    const int mt = 2 * (cl & 7) + rank, nt = cl >> 3;
#pragma unroll
    for (int kb = 0; kb < 3; kb++) {
      const uint32_t fb = bar + B_FULL + kb * 8, u0 = sbase + OFF_RING + kb * 3 * UNIT;
      mbar_expect_tx(fb, 16384 + 2 * 12288);
      tma_load_2d(u0, &p.xA, fb, kb * 64, mt * 128);
#pragma unroll
      for (int b = 0; b < 3; b++)
        tma_load_2d_mc(u0 + (1 + rank) * UNIT + b * 4096, &p.wqkv, fb, nt * 168 + b * 64, kb * 64 + rank * 32, 3);
    }
  }
  auto get_epoch = [&]() __attribute__((always_inline)) {
    mbar_wait(bar + B_EP, 0);
    return ld_shared_u32(bar + S_EPOCH);
  };

  const int hB = cl >> 2, prB = cl & 3;
  const int hA = cl >> 2;
  const int mpO = cl & 7, nhO = (cl >> 3) & 1, kspO = cl >> 4;

  if (warp >= 8) {
    reg_dealloc<REG_PROD>();
    if (warp == 8) {
      if (lane == 0) {
        ProdRing r;
        r.bar = bar;
        r.ring = sbase + OFF_RING;
        uint32_t epoch = 0;
        if (main_cl) {
          {
            const int mt = 2 * (cl & 7) + rank, nt = cl >> 3;
            r.g = 3;
            r.u = 0;
            r.free_units = 0;
            r.lens = 0x333;
            for (int kb = 3; kb < 7; kb++) {
              const uint32_t fb = r.acquire(3, 16384 + 2 * 12288);
              tma_load_2d(r.unit(0), &p.xA, fb, kb * 64, mt * 128);
              const uint32_t wd = r.unit(1 + rank);
#pragma unroll
              for (int b = 0; b < 3; b++)
                tma_load_2d_mc(wd + b * 4096, &p.wqkv, fb, nt * 168 + b * 64, kb * 64 + rank * 32, 3);
              r.next(3);
            }
          }
          const int g_long = rank == 0 ? 3 : 2, g_short = rank == 0 ? 0 : 1;
          auto qproj_group = [&](int tile, int kb) __attribute__((always_inline)) {
            const int m = tile == 0 ? 7 - prB : prB;
            const uint32_t fb = r.acquire(3, 49152, (tile == 0 && kb == 6) ? 1 : 0);
            tma_load_2d(r.unit(0), &p.xB, fb, kb * 64, 256 * m + 64 * (tile == 0 ? g_long : g_short));
            tma_load_2d(r.unit(0) + 8192, &p.xB, fb, kb * 64, 256 * m + 64 * (tile == 0 ? g_short : g_long));
            tma_load_3d_mc(r.unit(1 + rank), &p.wq3, fb, 0, kb * 64 + rank * 32, hB * 4, 3);
            r.next(3);
          };
          {
            for (int i = 0; i < 71; i++) {
              if (i < 64) {
                const int t = cl + (i >> 4) * 64;
                const int nt = t >> 3, mp = t & 7, kb = i & 15;
                const uint32_t fb = r.acquire(3, 49152);
                tma_load_2d(r.unit(0), &p.c, fb, kb * 64, mp * 256 + rank * 128);
                tma_load_3d_mc(r.unit(1 + rank), nt < 16 ? &p.wuk3 : &p.wuv3, fb, 0, kb * 64 + rank * 32, (nt & 15) * 4, 3);
                r.next(3);
              } else {
                qproj_group(0, i - 64);
              }
            }
          }
          {
            r.nu = NU;
            epoch = get_epoch();
            flag_wait(p.flags + F_KV + hB, epoch * 64);
            fence_proxy_async_global();
            for (int tile = 0; tile < 2; tile++) {
              const int N = 4 * (tile == 0 ? 7 - prB : prB) + 4;
              if (tile == 1)
                for (int kb = 0; kb < 7; kb++) qproj_group(1, kb);
              for (int s = 0; s < 2 * N; s++) {
                const bool isk = (s == 0) || ((s & 1) && s != 2 * N - 1);
                const int j = s == 2 * N - 1 ? N - 1 : (isk ? (s + 1) >> 1 : (s >> 1) - 1);
                const uint32_t fb = r.acquire(2, 32768);
                if (isk) tma_load_3d_mc(r.unit(rank), &p.kv3, fb, 0, hB * 2048 + j * 64, rank * 2, 3);
                else tma_load_3d_mc(r.unit(rank), &p.v3, fb, 0, (16 + hB) * 2048 + j * 64 + rank * 32, 0, 3);
                r.next(2);
              }
            }
          }
          {
            for (int kb = 0; kb < 16; kb++) {
              const int hh = kspO * 4 + ((hB + (kb >> 2)) & 3);
              const bool own = mpO < 4 && kb < 4;
              const uint32_t fb = r.acquire(3, own ? 32768 : 49152);
              const uint32_t wd = r.unit(1 + rank);
#pragma unroll
              for (int b = 0; b < 4; b++)
                tma_load_2d_mc(wd + b * 4096, &p.woB, fb, nhO * 224 + b * 64, hh * 256 + (kb & 3) * 64 + rank * 32, 3);
              if (!own) {
                if ((kb & 3) == 0) {
                  mbar_wait(bar + B_CX + (kb >> 2) * 8, 0);
                  fence_proxy_async_global();
                }
                tma_load_2d(r.unit(0), &p.ctx, fb, (kb & 3) * 64, hh * 2048 + mpO * 256 + 64 * g_short);
                tma_load_2d(r.unit(0) + 8192, &p.ctx, fb, (kb & 3) * 64, hh * 2048 + mpO * 256 + 64 * g_long);
              }
              r.next(3);
            }
          }
        } else {
          epoch = get_epoch();
          flag_wait(p.flags + F_OA, epoch * 512);
          fence_proxy_async_global();
          for (int it = 0; it < 8; it++) {
            const int mp = (cl - 64) * 4 + (it >> 1), nh = it & 1;
            for (int kb = 0; kb < 7; kb++) {
              const uint32_t fb = r.acquire(3, 49152);
              tma_load_2d(r.unit(0), &p.oA, fb, kb * 64, mp * 256 + rank * 128);
              const uint32_t wd = r.unit(1 + rank);
#pragma unroll
              for (int b = 0; b < 4; b++)
                tma_load_2d_mc(wd + b * 4096, &p.woA, fb, nh * 224 + b * 64, kb * 64 + rank * 32, 3);
              r.next(3);
            }
          }
        }
      }
      __syncwarp();
    } else if (warp < 11) {
      if (lane == 0) {
        const int wg = warp - 9;
        const uint32_t priv = sbase + wg * 32768;
        const uint32_t rdy = bar + B_STRDY + wg * 8, fre = bar + B_STFREE + wg * 8;
        uint32_t job = 0;
        auto begin = [&]() __attribute__((always_inline)) { mbar_wait(rdy, job & 1); };
        auto end = [&](uint32_t* flag, bool published = true) __attribute__((always_inline)) {
          tma_store_commit();
          tma_store_wait_read<0>();
          mbar_arrive(fre);
          job++;
          if (flag) {
            if (published) {
              tma_store_wait<0>();
              red_relaxed_gpu(flag, 1u);
            } else {
              red_release_gpu(flag, 1u);
            }
          }
        };
        if (main_cl) {
          {
            const int mt = 2 * (cl & 7) + rank, nt = cl >> 3;
            begin();
#pragma unroll
            for (int s = 0; s < 6; s++)
              tma_store_2d(&p.qkvA, priv + s * 4096, 0, (nt * 6 + s) * 2048 + mt * 128 + wg * 64);
            end(p.flags + F_A);
          }
          {
            for (int w = 0; w < 4; w++) {
              const int t = cl + w * 64;
              const int nt = t >> 3, mp = t & 7;
              const int grow = nt * 2048 + mp * 256 + rank * 128 + wg * 64;
              begin();
#pragma unroll 1
              for (int ch = 0; ch < 4; ch++) {
                tma_store_3d(&p.kv_st1, priv + ch * 8192, 0, grow, ch);
                if (ch < 3) pace(STORE_GAP);
              }
              end(p.flags + F_KV + (nt & 15));
              if (w == 1 || w == 3) {
                begin();
                end(p.flags + F_OA, false);
              }
            }
          }
          {
            for (int tile = 0; tile < 2; tile++) {
              const int m = tile == 0 ? 7 - prB : prB;
              const int g = (wg == tile) ? (rank == 0 ? 3 : 2) : (rank == 0 ? 0 : 1);
              begin();
#pragma unroll 1
              for (int ch = 0; ch < 4; ch++) {
                tma_store_2d(&p.ctx, priv + ch * 8192, ch * 64, hB * 2048 + 256 * m + 64 * g);
                if (ch < 3) pace(tile == 0 ? CTX0_GAP : CTX1_GAP);
              }
              end(p.flags + F_CTX + hB * 8 + m);
            }
          }
          {
            begin();
            tma_store_2d(&p.outB, priv, 448 + nhO * 224 + kspO * 56,
                         mpO * 256 + 64 * (wg == 1 ? (rank == 0 ? 3 : 2) : (rank == 0 ? 0 : 1)));
            end(nullptr);
          }
        } else {
          for (int it = 0; it < 8; it++) {
            const int mp = (cl - 64) * 4 + (it >> 1), nh = it & 1;
            begin();
            tma_store_2d(&p.outA, priv, nh * 224, mp * 256 + rank * 128 + wg * 64);
            end(nullptr);
          }
        }
        tma_store_wait<0>();
      }
      __syncwarp();
    } else {
      uint32_t epoch = 0;
      if (lane == 0) {
        epoch = atomicAdd(p.flags + F_TICKET, 1u) / NCTA + 1;
        st_shared_u32(bar + S_EPOCH, epoch);
        mbar_arrive(bar + B_EP);
      }
      if (lane == 0 && main_cl) {
        flag_wait(p.flags + F_A, epoch * 256);
        mbar_arrive(bar + B_FA);
        fence_proxy_async_global();
        for (int a = 0; a <= 64; a++) {
          const uint32_t fb = bar + B_AF + (a & 1) * 8;
          mbar_wait(bar + B_AE + (a & 1) * 8, ((a >> 1) & 1) ^ 1);
          mbar_expect_tx(fb, (a > 0 && a < 64) ? 8192 : 4096);
          if (rank == 0) {
            if (a < 64) tma_load_2d_mc(sbase + OFF_AK + (a & 1) * 4096, &p.qkvA, fb, 0, (16 + hA) * 2048 + (a & 31) * 64, 3);
          } else if (a > 0) {
            tma_load_2d_mc(sbase + OFF_AV + (a & 1) * 4096, &p.qkvA, fb, 0, (32 + hA) * 2048 + ((a - 1) & 31) * 64, 3);
          }
        }
        for (int k = mpO < 4 ? 1 : 0; k < 4; k++) {
          flag_wait_sleep(p.flags + F_CTX + (kspO * 4 + ((hB + k) & 3)) * 8 + mpO, epoch * 4);
          mbar_arrive(bar + B_CX + k * 8);
        }
      }
      __syncwarp();
    }
    cluster_arrive_relaxed();
    cluster_wait();
  } else {
    reg_alloc<REG_CONS>();
    Cons c;
    c.g = 0;
    uint32_t cur_off = 0, nu = NU1;
    StoreCtl st;
    st.jobs = 0;
#define CONSUMER_IDS()                                                          \
    const Ids id = make_ids();                                                  \
    const int cl = id.cl, wg = id.wg, wq = id.wq, lane = id.lane;               \
    const uint32_t rank = id.rank, sbase = id.sbase, bar = sbase + OFF_BAR;     \
    const uint32_t priv = sbase + wg * 32768;                                   \
    c.bar = bar;                                                                \
    c.ring16 = a16(sbase) + (OFF_RING >> 4);                                    \
    c.last16 = c.ring16 + (nu - 1) * (UNIT >> 4);                               \
    c.cur = c.ring16 + cur_off;                                                 \
    c.rel = mapa(bar + B_EMPTY, wq & 1);           \
    c.rel_thread = (wq < 2) && (lane == 0);                                     \
    st.rdy = bar + B_STRDY + wg * 8;                                            \
    st.fre = bar + B_STFREE + wg * 8;                                           \
    (void)cl; (void)rank; (void)priv

    if (main_cl) {
      float acc[128];
      float S[32];
      uint32_t P[16];
      {
        CONSUMER_IDS();
        float (&a84)[84] = reinterpret_cast<float (&)[84]>(acc);
        gemm_loop<168>(a84, c, wg, 7);
        cur_off = c.cur - c.ring16;
        const int nt = cl >> 3;
        const int row = wq * 16 + (lane >> 2);
        const uint32_t rb = priv + row * 64, sw = (row >> 1) & 3;
#pragma unroll
        for (int j = 0; j < 21; j++) {
          const int col = 8 * j + 2 * (lane & 3);
          const int hs = col / 28, d = col - hs * 28;
          const uint32_t ad = rb + hs * 4096 + (((d >> 3) ^ sw) << 4) + (d & 7) * 2;
          st_shared_u32(ad, pack_bf16(a84[4 * j], a84[4 * j + 1]));
          st_shared_u32(ad + 512, pack_bf16(a84[4 * j + 2], a84[4 * j + 3]));
          if (d == 26) {
            const uint32_t pad = nt * 6 + hs >= 32 ? 0x00003F80u : 0u;
            st_shared_u32(ad + 4, pad);
            st_shared_u32(ad + 8, 0u);
            st_shared_u32(ad + 516, pad);
            st_shared_u32(ad + 520, 0u);
          }
        }
        st.submit(lane);
      }
      {
        CONSUMER_IDS();
        const int hA = cl >> 2, qrowA = ((cl & 3) * 2 + rank) * 256;
        AttnA A;
        const uint32_t arel = mapa(bar + B_AE, wq & 1);
        const uint32_t ak16 = a16(sbase) + (OFF_AK >> 4), av16 = a16(sbase) + (OFF_AV >> 4);
        auto load_q = [&](int pass) __attribute__((always_inline)) {
          const bf16* q = p.qkvA_p + ((size_t)hA * 2048 + qrowA + pass * 128 + wg * 64 + wq * 16 + (lane >> 2)) * 32 + 2 * (lane & 3);
#pragma unroll
          for (int ks = 0; ks < 2; ks++) {
            A.Q[4 * ks + 0] = __ldcg(reinterpret_cast<const uint32_t*>(q + ks * 16));
            A.Q[4 * ks + 1] = __ldcg(reinterpret_cast<const uint32_t*>(q + ks * 16 + 8 * 32));
            A.Q[4 * ks + 2] = __ldcg(reinterpret_cast<const uint32_t*>(q + ks * 16 + 8));
            A.Q[4 * ks + 3] = __ldcg(reinterpret_cast<const uint32_t*>(q + ks * 16 + 8 + 8 * 32));
          }
        };
        auto issue_pv_a = [&](int a, int accumulate) __attribute__((always_inline)) {
          const uint32_t va = av16 + (a & 1) * 256;
#pragma unroll
          for (int ks = 0; ks < 4; ks++)
            wgmma_rs_n32_t(A.O, P[4 * ks], P[4 * ks + 1], P[4 * ks + 2], P[4 * ks + 3], desc_64(va + ks * 64),
                           ks == 0 ? accumulate : 1);
        };
        bool ok = false;
        const uint32_t ub0 = c.ring16;
        uint32_t ub = c.cur;
        auto gemm_tail = [&](int i) __attribute__((always_inline)) {
          c.g++;
          ub = (ub == ub0 + 6 * 1024) ? ub0 : ub + 3 * 1024;
          if ((i & 15) == 15 && i < 64) {
            wg_wait<0>();
            reg_fence(acc);
            c.release(c.g - 1);
            st.wait_free();
            store_acc_sw128<0, 32, 128>(acc, priv, wq, lane, 1.f, 1.f);
            st.submit(lane);
          }
        };
        auto plain_step = [&](int i) __attribute__((always_inline)) {
          if (!ok) c.wait(c.g);
          reg_fence(acc);
          wg_fence();
          issue_gemm256c(acc, ub, wg, (i & 15) == 0);
          wg_commit();
          ok = c.test(c.g + 1);
          if (i > 0) {
            wg_wait<1>();
            if ((i & 15) != 0) c.release(c.g - 1);
          }
          gemm_tail(i);
        };
#pragma unroll 1
        for (int i = 0; i < DA - 1; i++) plain_step(i);
        mbar_wait(bar + B_FA, 0);
        load_q(0);
        plain_step(DA - 1);
        bool oka = false;
#pragma unroll
        for (int q = 0; q < 16; q++) A.O[q] = 0.f;
#pragma unroll 1
        for (int pass = 0; pass < 2; pass++) {
          float m0 = -INFINITY, m1 = -INFINITY;
#pragma unroll
          for (int q = 0; q < 16; q++) P[q] = 0u;
#pragma unroll 2
          for (int j = 0; j < 32; j++) {
            const int a = pass * 32 + j, i = a + DA + pass;
            wg_wait<0>();
            if ((i & 15) != 0 || i > 64) c.release(c.g - 1);
            if (!ok) c.wait(c.g);
            if (!oka) mbar_wait(bar + B_AF + (a & 1) * 8, (a >> 1) & 1);
            reg_fence(S); reg_fence(A.O); reg_fence(P); reg_fence(A.Q); reg_fence(acc);
            wg_fence();
            {
              const uint32_t ka = ak16 + (a & 1) * 256;
              wgmma_rs_n64(S, A.Q[0], A.Q[1], A.Q[2], A.Q[3], desc_64(ka), 0);
              wgmma_rs_n64(S, A.Q[4], A.Q[5], A.Q[6], A.Q[7], desc_64(ka + 2), 1);
              issue_pv_a(a, j != 1);
              wg_commit();
              issue_gemm256c(acc, ub, wg, (i & 15) == 0);
              wg_commit();
            }
            wg_wait<1>();
            reg_fence(S); reg_fence(A.O); reg_fence(P);
            if (c.rel_thread) mbar_arrive_cluster(arel + (a & 1) * 8);
            float x0, x1;
            row_max64(S, x0, x1);
            const float n0 = fmaxf(m0, x0), n1 = fmaxf(m1, x1);
            const float a0 = ex2((m0 - n0) * SC_A), a1 = ex2((m1 - n1) * SC_A);
            m0 = n0;
            m1 = n1;
            const float c0 = n0 * SC_A, c1 = n1 * SC_A;
#pragma unroll
            for (int q = 0; q < 8; q++) {
              S[4 * q + 0] = ex2(fmaf(S[4 * q + 0], SC_A, -c0));
              S[4 * q + 1] = ex2(fmaf(S[4 * q + 1], SC_A, -c0));
              S[4 * q + 2] = ex2(fmaf(S[4 * q + 2], SC_A, -c1));
              S[4 * q + 3] = ex2(fmaf(S[4 * q + 3], SC_A, -c1));
            }
            pack_p(S, P);
#pragma unroll
            for (int q = 0; q < 4; q++) {
              A.O[4 * q + 0] *= a0;
              A.O[4 * q + 1] *= a0;
              A.O[4 * q + 2] *= a1;
              A.O[4 * q + 3] *= a1;
            }
            gemm_tail(i);
            ok = c.test(c.g);
            oka = mbar_test(bar + B_AF + ((a + 1) & 1) * 8, ((a + 1) >> 1) & 1);
          }
          {
            const int a = pass * 32 + 32;
            if (pass == 0) load_q(1);
            if (!oka) mbar_wait(bar + B_AF + (a & 1) * 8, (a >> 1) & 1);
            oka = true;
            reg_fence(A.O); reg_fence(P);
            wg_fence();
            issue_pv_a(a, 1);
            wg_commit();
            wg_wait<0>();
            reg_fence(A.O);
            const float l0 = __shfl_sync(0xffffffffu, A.O[12], (lane & ~3) | 2);
            const float l1 = __shfl_sync(0xffffffffu, A.O[14], (lane & ~3) | 2);
            const float i0 = rcp_fast(l0), i1 = rcp_fast(l1);
            const int row = qrowA + pass * 128 + wg * 64 + wq * 16 + (lane >> 2);
            bf16* o = p.oA_p + (size_t)row * 448 + hA * 28 + 2 * (lane & 3);
#pragma unroll
            for (int j = 0; j < 4; j++) {
              if (j < 3 || (lane & 3) < 2) {
                *reinterpret_cast<uint32_t*>(o + 8 * j) = pack_bf16(A.O[4 * j] * i0, A.O[4 * j + 1] * i0);
                *reinterpret_cast<uint32_t*>(o + 8 * j + 8 * 448) = pack_bf16(A.O[4 * j + 2] * i1, A.O[4 * j + 3] * i1);
              }
            }
            st.signal(lane);
            if (pass == 0) plain_step(DA + 32);
          }
        }
        static_assert(DA + 65 == 71, "64 fused steps + DA + 1 plain steps make up the 71 GEMM steps of phase 1");
        wg_wait<0>();
        reg_fence(acc);
        c.release(c.g - 1);
        cur_off = ub - ub0;
      }
      {
        nu = NU;
#pragma unroll 1
        for (int tile = 0; tile < 2; tile++) {
          CONSUMER_IDS();
          if (tile == 1) {
            gemm_loop<256>(acc, c, wg, 7);
          }
          attention_b_tile(acc, S, P, c, st, priv, wg, wq, lane, tile, tile == 0 ? 7 - (cl & 3) : (cl & 3), rank);
          cur_off = c.cur - c.ring16;
        }
      }
      {
        CONSUMER_IDS();
        const int mpO = cl & 7, nhO = (cl >> 3) & 1, kspO = cl >> 4;
        float (&a112)[112] = reinterpret_cast<float (&)[112]>(acc);
        {
          const int nown = mpO < 4 ? 4 : 0;
          const uint32_t own16 = a16(priv);
          named_bar_sync(BAR_WG0 + wg, 128);
          bool ok = false;
#pragma unroll 1
          for (int kb = 0; kb < 16; kb++) {
            if (!ok) c.wait(c.g);
            const uint32_t xa = kb < nown ? own16 + kb * 512 : c.cur + wg * 512;
            const uint32_t w0 = c.adv(c.cur), w1 = c.adv(w0);
            reg_fence(a112);
            wg_fence();
            wgmma_ss_n224_t(a112, desc_k128(xa), desc_mn128h(w0), kb != 0);
            wgmma_ss_n224_t(a112, desc_k128(xa + 2), desc_mn128h(w0 + 128), 1);
            wgmma_ss_n224_t(a112, desc_k128(xa + 4), desc_mn128h(w1), 1);
            wgmma_ss_n224_t(a112, desc_k128(xa + 6), desc_mn128h(w1 + 128), 1);
            wg_commit();
            if (kb > 0) {
              wg_wait<1>();
              c.release(c.g - 1);
            }
            ok = c.test(c.g + 1);
            c.g++;
            c.cur = c.adv(w1);
          }
          wg_wait<0>();
          reg_fence(a112);
          c.release(c.g - 1);
        }
        const int grp = (mpO * 2 + nhO) * 2 + rank;
        const int tid = wg * 128 + wq * 32 + lane;
        float4* const part = p.part + (size_t)grp * (12 * 7 * 256) + tid;
#pragma unroll
        for (int q = 0; q < 4; q++) {
          if (q != kspO) {
            float4* dst = part + (q * 3 + (kspO > q ? kspO - 1 : kspO)) * (7 * 256);
#pragma unroll
            for (int j = 0; j < 7; j++) {
              const int jj = q * 7 + j;
              __stcg(dst + j * 256, make_float4(a112[4 * jj], a112[4 * jj + 1], a112[4 * jj + 2], a112[4 * jj + 3]));
            }
          }
        }
        named_bar_sync(BAR_WG0 + wg, 128);
        if (wq == 0 && lane == 0) {
          red_release_gpu(p.flags + F_X + grp * 2 + wg, 1u);
          mbar_wait(bar + B_EP, 0);
          flag_wait(p.flags + F_X + grp * 2 + wg, ld_shared_u32(bar + S_EPOCH) * 4);
        }
        named_bar_sync(BAR_WG0 + wg, 128);
#pragma unroll
        for (int q = 0; q < 4; q++) {
          if (q == kspO) {
            float4 v[21];
            const float4* sp = part + q * 3 * (7 * 256);
#pragma unroll
            for (int j = 0; j < 21; j++) v[j] = __ldcg(sp + j * 256);
            st.wait_free();
            const uint32_t ad = priv + (wq * 16 + (lane >> 2)) * 112 + (lane & 3) * 4;
#pragma unroll
            for (int j = 0; j < 7; j++) {
              const int jj = q * 7 + j;
              float r0 = a112[4 * jj], r1 = a112[4 * jj + 1], r2 = a112[4 * jj + 2], r3 = a112[4 * jj + 3];
#pragma unroll
              for (int s3 = 0; s3 < 3; s3++) {
                r0 += v[s3 * 7 + j].x;
                r1 += v[s3 * 7 + j].y;
                r2 += v[s3 * 7 + j].z;
                r3 += v[s3 * 7 + j].w;
              }
              st_shared_u32(ad + j * 16, pack_bf16(r0, r1));
              st_shared_u32(ad + j * 16 + 8 * 112, pack_bf16(r2, r3));
            }
            st.submit(lane);
          }
        }
      }
    } else {
      CONSUMER_IDS();
      float acc[112];
#pragma unroll 1
      for (int it = 0; it < 8; it++) {
        gemm_loop<224>(acc, c, wg, 7);
        st.wait_free();
        const uint32_t ad = priv + (wq * 16 + (lane >> 2)) * 448 + (lane & 3) * 4;
#pragma unroll
        for (int j = 0; j < 28; j++) {
          st_shared_u32(ad + j * 16, pack_bf16(acc[4 * j], acc[4 * j + 1]));
          st_shared_u32(ad + j * 16 + 8 * 448, pack_bf16(acc[4 * j + 2], acc[4 * j + 3]));
        }
        st.submit(lane);
      }
    }
    cluster_arrive_relaxed();
    cluster_wait();
  }
}

__device__ __align__(1024) bf16 g_kv[32 * 2048 * 256];
__device__ __align__(1024) bf16 g_ctx[16 * 2048 * 256];
__device__ __align__(1024) bf16 g_qkvA[48 * 2048 * 32];
__device__ __align__(1024) bf16 g_oA[2048 * 448];
__device__ __align__(1024) float4 g_part[32 * 12 * 7 * 256];
__device__ __align__(1024) uint32_t g_flags[mk::F_COUNT];

typedef CUresult (*PFN_encodeTiled)(CUtensorMap*, CUtensorMapDataType, cuuint32_t, void*, const cuuint64_t*,
                                    const cuuint64_t*, const cuuint32_t*, const cuuint32_t*, CUtensorMapInterleave,
                                    CUtensorMapSwizzle, CUtensorMapL2promotion, CUtensorMapFloatOOBfill);

static void make_map2(PFN_encodeTiled enc, CUtensorMap* tm, const void* base, uint64_t cols, uint64_t rows,
                      uint32_t box_cols, uint32_t box_rows, CUtensorMapSwizzle sw) {
  cuuint64_t dims[2] = {cols, rows};
  cuuint64_t strides[1] = {cols * 2};
  cuuint32_t box[2] = {box_cols, box_rows};
  cuuint32_t estr[2] = {1, 1};
  enc(tm, CU_TENSOR_MAP_DATA_TYPE_BFLOAT16, 2, const_cast<void*>(base), dims, strides, box, estr,
      CU_TENSOR_MAP_INTERLEAVE_NONE, sw, CU_TENSOR_MAP_L2_PROMOTION_L2_256B, CU_TENSOR_MAP_FLOAT_OOB_FILL_NONE);
}
static void make_map3(PFN_encodeTiled enc, CUtensorMap* tm, const void* base, uint64_t cols, uint64_t rows,
                      uint32_t box_rows, uint32_t box_chunks) {
  cuuint64_t dims[3] = {64, rows, cols / 64};
  cuuint64_t strides[2] = {cols * 2, 128};
  cuuint32_t box[3] = {64, box_rows, box_chunks};
  cuuint32_t estr[3] = {1, 1, 1};
  enc(tm, CU_TENSOR_MAP_DATA_TYPE_BFLOAT16, 3, const_cast<void*>(base), dims, strides, box, estr,
      CU_TENSOR_MAP_INTERLEAVE_NONE, CU_TENSOR_MAP_SWIZZLE_128B, CU_TENSOR_MAP_L2_PROMOTION_L2_256B,
      CU_TENSOR_MAP_FLOAT_OOB_FILL_NONE);
}

extern "C" void kernel_launch(void* const* d_in, const int* in_sizes, int n_in, void* d_out, int out_size) {
  (void)in_sizes; (void)n_in; (void)out_size;
  static PFN_encodeTiled enc = nullptr;
  if (!enc) {
    void* fn = nullptr;
    cudaDriverEntryPointQueryResult qr;
    cudaGetDriverEntryPoint("cuTensorMapEncodeTiled", &fn, cudaEnableDefault, &qr);
    enc = (PFN_encodeTiled)fn;
    cudaFuncSetAttribute(k_mega, cudaFuncAttributeMaxDynamicSharedMemorySize, mk::SMEM);
  }
  void *p_kv, *p_ctx, *p_qkvA, *p_oA, *p_part, *p_flags;
  cudaGetSymbolAddress(&p_kv, g_kv);
  cudaGetSymbolAddress(&p_ctx, g_ctx);
  cudaGetSymbolAddress(&p_qkvA, g_qkvA);
  cudaGetSymbolAddress(&p_oA, g_oA);
  cudaGetSymbolAddress(&p_part, g_part);
  cudaGetSymbolAddress(&p_flags, g_flags);
  const CUtensorMapSwizzle S128 = CU_TENSOR_MAP_SWIZZLE_128B, S64 = CU_TENSOR_MAP_SWIZZLE_64B,
                           SNONE = CU_TENSOR_MAP_SWIZZLE_NONE;
  Params p;
  make_map2(enc, &p.xA, d_in[0], 448, 2048, 64, 128, S128);
  make_map2(enc, &p.wqkv, d_in[1], 1344, 448, 64, 32, S128);
  make_map2(enc, &p.woA, d_in[2], 448, 448, 64, 32, S128);
  make_map2(enc, &p.xB, d_in[3], 448, 2048, 64, 64, S128);
  make_map2(enc, &p.c, d_in[4], 1024, 2048, 64, 128, S128);
  make_map3(enc, &p.wq3, d_in[5], 4096, 448, 32, 4);
  make_map3(enc, &p.wuk3, d_in[6], 4096, 1024, 32, 4);
  make_map3(enc, &p.wuv3, d_in[7], 4096, 1024, 32, 4);
  make_map2(enc, &p.woB, d_in[8], 448, 4096, 64, 32, S128);
  make_map3(enc, &p.kv3, p_kv, 256, 32 * 2048, 64, 2);
  make_map3(enc, &p.kv_st1, p_kv, 256, 32 * 2048, 64, 1);
  make_map3(enc, &p.v3, p_kv, 256, 32 * 2048, 32, 4);
  make_map2(enc, &p.ctx, p_ctx, 256, 16 * 2048, 64, 64, S128);
  make_map2(enc, &p.qkvA, p_qkvA, 32, 48 * 2048, 32, 64, S64);
  make_map2(enc, &p.oA, p_oA, 448, 2048, 64, 128, S128);
  make_map2(enc, &p.outB, d_out, 896, 2048, 56, 64, SNONE);
  make_map2(enc, &p.outA, d_out, 896, 2048, 224, 64, SNONE);
  p.qkvA_p = (const bf16*)p_qkvA;
  p.oA_p = (bf16*)p_oA;
  p.part = (float4*)p_part;
  p.flags = (uint32_t*)p_flags;
  k_mega<<<mk::NCTA, 384, mk::SMEM>>>(p);
}
```
